```python
import torch

def _softmax(x, axis=-1):
    return torch.softmax(x, dim=axis)
def _gelu(x):
    return torch.nn.functional.gelu(x, approximate="tanh")
def _silu(x):
    return torch.nn.functional.silu(x)
def _sigmoid(x):
    return torch.sigmoid(x)
def _layernorm(x, axis=-1, eps=1e-5):
    m = x.mean(dim=axis, keepdim=True)
    v = x.var(dim=axis, keepdim=True, unbiased=False)
    return (x - m) / torch.sqrt(v + eps)
def _scatter_add(tgt, idx, src, axis=0):
    return tgt.clone().index_add_(axis, idx, src)
def _segment_sum(src, seg, n):
    out = torch.zeros((n,) + src.shape[1:], dtype=src.dtype)
    return out.index_add_(0, seg, src)
def _pad(x, pw):
    flat = tuple(v for pair in reversed(pw) for v in pair)
    return torch.nn.functional.pad(x, flat)

kernel_name = 'parallel_sum__sliding_block_cached__geglu_ffn__decode'

def setup_inputs():

    _w = (lambda a: (lambda t: t.to(torch.bfloat16) if t.is_floating_point() else t)(torch.as_tensor(a)))
    def _A_setup():
        B, Sq, D = 4, 1, 448
        Hq, Hkv, Sk, Dh = 16, 8, 4096, 256
        assert Hq % Hkv == 0, (Hq, Hkv)
        return {
            "x": _w((lambda *s: torch.randn(*s, dtype=torch.bfloat16) * 0.05)(B, Sq, D)),
            "k_cache": _w((lambda *s: torch.randn(*s, dtype=torch.bfloat16) * 3.2)(B, Hkv, Sk, Dh)),
            "v_cache": _w((lambda *s: torch.randn(*s, dtype=torch.bfloat16) * 1.6)(B, Hkv, Sk, Dh)),
            "wq": _w((lambda *s: torch.randn(*s, dtype=torch.bfloat16) * 3.2)(D, Hq * Dh) * (D ** -0.5)),
            "wo": _w((lambda *s: torch.randn(*s, dtype=torch.bfloat16) * 1.6)(Hq * Dh, D) * ((Hq * Dh) ** -0.5)),
        }
    _A_in = _A_setup()

    def _B_setup():
        B, S, D, F = 4, 1, 448, 1792
        return {
            "x": _w((lambda *s: torch.randn(*s, dtype=torch.bfloat16) * 0.05)(B, S, D)),
            "w_gate": _w((lambda *s: torch.randn(*s, dtype=torch.bfloat16) * 0.05)(D, F)),
            "w_up": _w((lambda *s: torch.randn(*s, dtype=torch.bfloat16) * 0.05)(D, F)),
            "w_down": _w((lambda *s: torch.randn(*s, dtype=torch.bfloat16) * 0.05)(F, D)),
        }
    _B_in = _B_setup()

    return {
        "A_x": _A_in["x"],
        "A_k_cache": _A_in["k_cache"],
        "A_v_cache": _A_in["v_cache"],
        "A_wq": _A_in["wq"],
        "A_wo": _A_in["wo"],
        "B_x": _B_in["x"],
        "B_w_gate": _B_in["w_gate"],
        "B_w_up": _B_in["w_up"],
        "B_w_down": _B_in["w_down"],
    }

def reference(A_x, A_k_cache, A_v_cache, A_wq, A_wo, B_x, B_w_gate, B_w_up, B_w_down):
    def _A_ref(x, k_cache, v_cache, wq, wo):
        B, Sq, D = x.shape
        Hq, Dh = 16, 256
        Hkv, Sk = k_cache.shape[1], k_cache.shape[2]
        W = min(4096, max(256, Sk // 4))
        rep = Hq // Hkv
        q = (lambda x, *d: x.permute(*d))((x @ wq).reshape(B, Sq, Hq, Dh), 0, 2, 1, 3)
        k = (lambda x, n, axis: torch.repeat_interleave(x, n, dim=axis))(k_cache[:, :, Sk - W:, :], rep, axis=1)
        v = (lambda x, n, axis: torch.repeat_interleave(x, n, dim=axis))(v_cache[:, :, Sk - W:, :], rep, axis=1)
        scores = torch.einsum("bhqd,bhkd->bhqk", q, k) * (Dh ** -0.5)
        p = _softmax(scores, axis=-1)
        o = torch.einsum("bhqk,bhkd->bhqd", p, v)
        return (lambda x, *d: x.permute(*d))(o, 0, 2, 1, 3).reshape(B, Sq, Hq * Dh) @ wo

    def _B_ref(x, w_gate, w_up, w_down):
        return (_gelu(x @ w_gate) * (x @ w_up)) @ w_down

    x = A_x
    xn = _layernorm(x, axis=-1)
    return x + _A_ref(xn, A_k_cache, A_v_cache, A_wq, A_wo) + _B_ref(xn, B_w_gate, B_w_up, B_w_down)
```

```cpp
#include <cuda_runtime.h>
#include <cuda_bf16.h>
#include <cuda.h>
#include <stdint.h>

namespace {

constexpr int NB   = 4;
constexpr int DM   = 448;
constexpr int HKV  = 8;
constexpr int SK   = 4096;
constexpr int WIN  = 1024;
constexpr int NCTA = 128;
constexpr int NFFN = 112;
constexpr int NOWN = 112;
constexpr int NTHREADS = 288;
constexpr int SLOT  = 16384;
constexpr int NSLOT = 13;

constexpr int OFF_BAR = NSLOT * SLOT;
constexpr int OFF_XN  = OFF_BAR + 256;
constexpr int OFF_QS  = OFF_XN + 4 * 228 * 4;
constexpr int OFF_SC  = OFF_QS + 1024;
constexpr int OFF_PB  = OFF_SC + 2048;
constexpr int OFF_HS  = OFF_PB + 1024;
constexpr int OFF_OS  = OFF_HS + 256;
constexpr int OFF_WM  = OFF_OS + 512;
constexpr int OFF_ST  = OFF_WM + 128;
constexpr int OFF_RED = OFF_ST + 128;
constexpr int SMEM_USED = OFF_RED + 2048;
constexpr int SMEM_BYTES = SMEM_USED + 1024;

__device__ unsigned int g_epoch;
__device__ unsigned int g_err;
__device__ __align__(128) unsigned long long g_q[HKV * NB * 512];
__device__ __align__(128) unsigned long long g_st[NB * HKV * 4 * 4];
__device__ __align__(128) unsigned long long g_o[NCTA * 16 * 32];
__device__ __align__(128) unsigned long long g_att[NOWN * NCTA * 16];
__device__ __align__(128) unsigned long long g_ffn[NOWN * NFFN * 16];

constexpr unsigned SPIN_LIMIT = 1u << 24;

__device__ __forceinline__ uint32_t smem_u32(const void* p) {
    return (uint32_t)__cvta_generic_to_shared(p);
}
__device__ __forceinline__ void mbar_init(uint32_t a, uint32_t cnt) {
    asm volatile("mbarrier.init.shared::cta.b64 [%0], %1;" ::"r"(a), "r"(cnt) : "memory");
}
__device__ __forceinline__ void mbar_expect_tx(uint32_t a, uint32_t bytes) {
    asm volatile("mbarrier.arrive.expect_tx.shared::cta.b64 _, [%0], %1;" ::"r"(a), "r"(bytes)
                 : "memory");
}
__device__ __forceinline__ void mbar_arrive(uint32_t a) {
    asm volatile("mbarrier.arrive.shared::cta.b64 _, [%0];" ::"r"(a) : "memory");
}
__device__ __forceinline__ bool mbar_try(uint32_t a, uint32_t parity) {
    uint32_t ok;
    asm volatile(
        "{\n\t.reg .pred p;\n\t"
        "mbarrier.try_wait.parity.shared::cta.b64 p, [%1], %2;\n\t"
        "selp.u32 %0, 1, 0, p;\n\t}"
        : "=r"(ok)
        : "r"(a), "r"(parity)
        : "memory");
    return ok != 0;
}
__device__ __forceinline__ void mbar_wait(uint32_t a, uint32_t parity) {
    unsigned it = 0;
    while (!mbar_try(a, parity)) {
        if (++it > SPIN_LIMIT) { g_err = 1; break; }
    }
}
__device__ __forceinline__ void tma_2d(uint32_t dst, const CUtensorMap* tm, int c0, int c1,
                                       uint32_t mbar) {
    asm volatile(
        "cp.async.bulk.tensor.2d.shared::cluster.global.mbarrier::complete_tx::bytes "
        "[%0], [%1, {%3, %4}], [%2];" ::"r"(dst),
        "l"(reinterpret_cast<uint64_t>(tm)), "r"(mbar), "r"(c0), "r"(c1)
        : "memory");
}
__device__ __forceinline__ void ldsm_x4(uint32_t (&r)[4], uint32_t a) {
    asm volatile("ldmatrix.sync.aligned.m8n8.x4.shared.b16 {%0,%1,%2,%3}, [%4];"
                 : "=r"(r[0]), "=r"(r[1]), "=r"(r[2]), "=r"(r[3])
                 : "r"(a)
                 : "memory");
}
__device__ __forceinline__ void ldsm_x4_t(uint32_t (&r)[4], uint32_t a) {
    asm volatile("ldmatrix.sync.aligned.m8n8.x4.trans.shared.b16 {%0,%1,%2,%3}, [%4];"
                 : "=r"(r[0]), "=r"(r[1]), "=r"(r[2]), "=r"(r[3])
                 : "r"(a)
                 : "memory");
}
__device__ __forceinline__ void mma_bf16(float (&d)[4], const uint32_t (&a)[4], uint32_t b0,
                                         uint32_t b1) {
    asm volatile(
        "mma.sync.aligned.m16n8k16.row.col.f32.bf16.bf16.f32 {%0,%1,%2,%3}, {%4,%5,%6,%7}, "
        "{%8,%9}, {%0,%1,%2,%3};"
        : "+f"(d[0]), "+f"(d[1]), "+f"(d[2]), "+f"(d[3])
        : "r"(a[0]), "r"(a[1]), "r"(a[2]), "r"(a[3]), "r"(b0), "r"(b1));
}
__device__ __forceinline__ void cons_sync() {
    asm volatile("bar.sync 1, 256;" ::: "memory");
}
template <int RBYTES>
__device__ __forceinline__ uint32_t swz(uint32_t base, int row, int chunk) {
    constexpr uint32_t MASK = RBYTES == 128 ? 7u : (RBYTES == 64 ? 3u : 1u);
    uint32_t off = (uint32_t)row * RBYTES + (uint32_t)chunk * 16u;
    return base + (off ^ (((off >> 7) & MASK) << 4));
}
__device__ __forceinline__ float bf16r(float v) {
    return __bfloat162float(__float2bfloat16_rn(v));
}
__device__ __forceinline__ uint32_t pack_bf16(float lo, float hi) {
    __nv_bfloat162 v = __floats2bfloat162_rn(lo, hi);
    return *reinterpret_cast<uint32_t*>(&v);
}
__device__ __forceinline__ void ll_store(unsigned long long* p, uint32_t payload, uint32_t tag) {
    unsigned long long v = ((unsigned long long)tag << 32) | payload;
    asm volatile("st.relaxed.gpu.global.b64 [%0], %1;" ::"l"(p), "l"(v) : "memory");
}
__device__ __forceinline__ uint32_t ll_poll(const unsigned long long* p, uint32_t tag) {
    unsigned long long v;
    unsigned it = 0;
    while (true) {
        asm volatile("ld.relaxed.gpu.global.b64 %0, [%1];" : "=l"(v) : "l"(p) : "memory");
        if ((uint32_t)(v >> 32) == tag) break;
        if (++it > SPIN_LIMIT) { g_err = 2; break; }
    }
    return (uint32_t)v;
}
__device__ __forceinline__ float warp_max(float v) {
#pragma unroll
    for (int o = 16; o > 0; o >>= 1) v = fmaxf(v, __shfl_xor_sync(0xffffffffu, v, o));
    return v;
}
__device__ __forceinline__ float warp_sum(float v) {
#pragma unroll
    for (int o = 16; o > 0; o >>= 1) v += __shfl_xor_sync(0xffffffffu, v, o);
    return v;
}
__device__ __forceinline__ float gelu_tanh(float x) {
    const float kBeta = 0.7978845608028654f, kKappa = 0.044715f;
    float inner = kBeta * (x + kKappa * x * x * x);
    return 0.5f * x * (1.0f + tanhf(inner));
}

__global__ void __launch_bounds__(NTHREADS, 1)
fused_decode_kernel(const __grid_constant__ CUtensorMap tm_k, const __grid_constant__ CUtensorMap tm_v,
                    const __grid_constant__ CUtensorMap tm_wq, const __grid_constant__ CUtensorMap tm_wg,
                    const __grid_constant__ CUtensorMap tm_wu, const __grid_constant__ CUtensorMap tm_wd,
                    const __grid_constant__ CUtensorMap tm_wo, const __nv_bfloat16* __restrict__ x,
                    __nv_bfloat16* __restrict__ out) {
    extern __shared__ uint8_t smem_raw[];
    uint8_t* smem = smem_raw + ((1024u - (smem_u32(smem_raw) & 1023u)) & 1023u);
    const uint32_t sb = smem_u32(smem);

    const int tid = threadIdx.x, warp = tid >> 5, lane = tid & 31;
    const int g = lane >> 2, j = lane & 3;
    const int cta = blockIdx.x;
    const int hkv = cta >> 4, rk = cta & 15;
    const int bat = rk >> 2, chunk = rk & 3;
    const bool has_ffn = cta < NFFN;

    auto full = [&](int s) { return sb + OFF_BAR + 8u * s; };
    auto empty = [&](int s) { return sb + OFF_BAR + 8u * (NSLOT + s); };
    auto slot = [&](int s) { return sb + (uint32_t)s * SLOT; };

    if (tid == 0) {
        for (int s = 0; s < NSLOT; s++) mbar_init(full(s), 1);
        mbar_init(empty(0), 2);
        mbar_init(empty(1), 2);
        mbar_init(empty(2), 1);
        mbar_init(empty(3), 1);
        mbar_init(empty(4), 7);
        for (int s = 5; s < NSLOT; s++) mbar_init(empty(s), 2);
        asm volatile("fence.mbarrier_init.release.cluster;" ::: "memory");
        asm volatile("fence.proxy.async.shared::cta;" ::: "memory");
    }
    __syncthreads();

    if (warp == 8) {
        if (lane == 0) {
            mbar_expect_tx(full(0), 14336);
            tma_2d(slot(0), &tm_wq, 32 * cta, 0, full(0));
            mbar_expect_tx(full(1), 14336);
            tma_2d(slot(1), &tm_wq, 32 * cta, 224, full(1));
            if (has_ffn) {
                mbar_expect_tx(full(2), 14336);
                tma_2d(slot(2), &tm_wg, 16 * cta, 0, full(2));
                tma_2d(slot(2) + 7168, &tm_wg, 16 * cta, 224, full(2));
                mbar_expect_tx(full(3), 14336);
                tma_2d(slot(3), &tm_wu, 16 * cta, 0, full(3));
                tma_2d(slot(3) + 7168, &tm_wu, 16 * cta, 224, full(3));
                mbar_expect_tx(full(4), 14336);
                for (int bx = 0; bx < 7; bx++)
                    tma_2d(slot(4) + bx * 2048, &tm_wd, 64 * bx, 16 * cta, full(4));
            }
            const int krow0 = (bat * HKV + hkv) * SK + (SK - WIN) + chunk * 256;
            for (int t = 0; t < 8; t++) {
                mbar_expect_tx(full(5 + t), 16384);
                for (int dg = 0; dg < 4; dg++)
                    tma_2d(slot(5 + t) + dg * 4096, &tm_k, 64 * dg, krow0 + 32 * t, full(5 + t));
            }
            for (int v = 0; v < 8; v++) {
                if (has_ffn || v < 2 || v > 4) mbar_wait(empty(v), 0);
                mbar_expect_tx(full(v), 16384);
                for (int dg = 0; dg < 4; dg++)
                    tma_2d(slot(v) + dg * 4096, &tm_v, 64 * dg, krow0 + 32 * v, full(v));
            }
            mbar_wait(empty(8), 0);
            mbar_expect_tx(full(8), 16384);
            for (int bx = 0; bx < 4; bx++)
                tma_2d(slot(8) + bx * 4096, &tm_wo, 64 * bx, 32 * cta, full(8));
            mbar_wait(empty(9), 0);
            mbar_expect_tx(full(9), 12288);
            for (int bx = 4; bx < 7; bx++)
                tma_2d(slot(9) + (bx - 4) * 4096, &tm_wo, 64 * bx, 32 * cta, full(9));
        }
        return;
    }

    uint32_t* xn_w = reinterpret_cast<uint32_t*>(smem + OFF_XN);
    uint32_t* qs_w = reinterpret_cast<uint32_t*>(smem + OFF_QS);
    float* sc = reinterpret_cast<float*>(smem + OFF_SC);
    uint32_t* pb_w = reinterpret_cast<uint32_t*>(smem + OFF_PB);
    uint32_t* hs_w = reinterpret_cast<uint32_t*>(smem + OFF_HS);
    uint32_t* os_w = reinterpret_cast<uint32_t*>(smem + OFF_OS);
    float* wm = reinterpret_cast<float*>(smem + OFF_WM);
    float* stt = reinterpret_cast<float*>(smem + OFF_ST);
    float* red = reinterpret_cast<float*>(smem + OFF_RED);

    unsigned int epoch;
    asm volatile("ld.relaxed.gpu.global.u32 %0, [%1];" : "=r"(epoch) : "l"(&g_epoch) : "memory");
    const uint32_t tag = epoch + 1u;

    if (warp >= 4) {
        const int br = warp - 4;
        const uint32_t* xw = reinterpret_cast<const uint32_t*>(x) + br * (DM / 2);
        float2 v[7];
        float s = 0.f;
#pragma unroll
        for (int e = 0; e < 7; e++) {
            uint32_t u = __ldg(xw + lane + 32 * e);
            __nv_bfloat162 h = *reinterpret_cast<__nv_bfloat162*>(&u);
            v[e] = __bfloat1622float2(h);
            s += v[e].x + v[e].y;
        }
        const float mean = warp_sum(s) * (1.0f / DM);
        float q2 = 0.f;
#pragma unroll
        for (int e = 0; e < 7; e++) {
            float a = v[e].x - mean, c = v[e].y - mean;
            q2 += a * a + c * c;
        }
        const float var = warp_sum(q2) * (1.0f / DM);
        const float m_b = bf16r(mean), v_b = bf16r(var);
        const float den = bf16r(sqrtf(bf16r(v_b + 1e-5f)));
#pragma unroll
        for (int e = 0; e < 7; e++) {
            float a = bf16r(v[e].x - m_b) / den, c = bf16r(v[e].y - m_b) / den;
            xn_w[br * 228 + lane + 32 * e] = pack_bf16(a, c);
        }
    }
    cons_sync();

    if (warp < 2) {
        float acc0[4] = {0.f, 0.f, 0.f, 0.f}, acc1[4] = {0.f, 0.f, 0.f, 0.f};
        const int mat = lane >> 3, r8 = lane & 7;
#pragma unroll
        for (int h = 0; h < 2; h++) {
            mbar_wait(full(h), 0);
#pragma unroll
            for (int ks = 0; ks < 14; ks++) {
                uint32_t a[4];
                ldsm_x4_t(a, swz<64>(slot(h), ks * 16 + (mat >> 1) * 8 + r8, warp * 2 + (mat & 1)));
                const int kw = (h * 14 + ks) * 8;
                uint32_t b0 = g < 4 ? xn_w[g * 228 + kw + j] : 0u;
                uint32_t b1 = g < 4 ? xn_w[g * 228 + kw + 4 + j] : 0u;
                if (ks & 1) mma_bf16(acc1, a, b0, b1);
                else mma_bf16(acc0, a, b0, b1);
            }
            __syncwarp();
            if (lane == 0) mbar_arrive(empty(h));
        }
        if (j < 2) {
            unsigned long long* dst = g_q + (size_t)(hkv * NB) * 512 + rk * 32 + warp * 16 + g;
#pragma unroll
            for (int c = 0; c < 4; c++) {
                const int bb = 2 * j + (c & 1), nn = (c >> 1) * 8;
                float qv = bf16r(acc0[c] + acc1[c]);
                ll_store(dst + bb * 512 + nn, __float_as_uint(qv), tag);
            }
        }
    } else if (warp == 2 && has_ffn) {
        float ag[4] = {0.f, 0.f, 0.f, 0.f}, au[4] = {0.f, 0.f, 0.f, 0.f};
        const int mat = lane >> 3, r8 = lane & 7;
        mbar_wait(full(2), 0);
        mbar_wait(full(3), 0);
#pragma unroll
        for (int h = 0; h < 2; h++) {
#pragma unroll
            for (int ks = 0; ks < 14; ks++) {
                uint32_t a[4], a2[4];
                const int row = ks * 16 + (mat >> 1) * 8 + r8;
                ldsm_x4_t(a, swz<32>(slot(2) + h * 7168, row, mat & 1));
                ldsm_x4_t(a2, swz<32>(slot(3) + h * 7168, row, mat & 1));
                const int kw = (h * 14 + ks) * 8;
                uint32_t b0 = g < 4 ? xn_w[g * 228 + kw + j] : 0u;
                uint32_t b1 = g < 4 ? xn_w[g * 228 + kw + 4 + j] : 0u;
                mma_bf16(ag, a, b0, b1);
                mma_bf16(au, a2, b0, b1);
            }
        }
        __syncwarp();
        if (lane == 0) { mbar_arrive(empty(2)); mbar_arrive(empty(3)); }
        if (j < 2) {
            __nv_bfloat16* hs = reinterpret_cast<__nv_bfloat16*>(hs_w);
#pragma unroll
            for (int c = 0; c < 4; c++) {
                const int bb = 2 * j + (c & 1), ff = g + (c >> 1) * 8;
                float gv = bf16r(gelu_tanh(bf16r(ag[c])));
                float hv = gv * bf16r(au[c]);
                hs[bb * 24 + ff] = __float2bfloat16_rn(hv);
            }
        }
    }
    cons_sync();

    if (has_ffn && warp < 7) {
        const int mat = lane >> 3, r8 = lane & 7;
        const uint32_t b0 = g < 4 ? hs_w[g * 12 + j] : 0u;
        const uint32_t b1 = g < 4 ? hs_w[g * 12 + 4 + j] : 0u;
        mbar_wait(full(4), 0);
#pragma unroll
        for (int i = 0; i < 4; i++) {
            uint32_t a[4];
            ldsm_x4_t(a, swz<128>(slot(4) + warp * 2048, (mat >> 1) * 8 + r8, i * 2 + (mat & 1)));
            float d[4] = {0.f, 0.f, 0.f, 0.f};
            mma_bf16(d, a, b0, b1);
            if (j < 2) {
                const int mt = warp * 4 + i;
#pragma unroll
                for (int c = 0; c < 4; c++) {
                    const int bb = 2 * j + (c & 1), e = g + (c >> 1) * 8;
                    ll_store(g_ffn + ((size_t)(bb * 28 + mt) * NFFN + cta) * 16 + e,
                             __float_as_uint(d[c]), tag);
                }
            }
        }
        __syncwarp();
        if (lane == 0) mbar_arrive(empty(4));
    }

    {
        const unsigned long long* src = g_q + (size_t)(hkv * NB + bat) * 512 + 2 * tid;
        float q0 = __uint_as_float(ll_poll(src, tag));
        float q1 = __uint_as_float(ll_poll(src + 1, tag));
        qs_w[tid] = pack_bf16(q0, q1);
    }
    cons_sync();

    {
        uint32_t qb[32];
#pragma unroll
        for (int s = 0; s < 16; s++) {
            qb[2 * s] = g < 2 ? qs_w[g * 128 + 8 * s + j] : 0u;
            qb[2 * s + 1] = g < 2 ? qs_w[g * 128 + 8 * s + 4 + j] : 0u;
        }
        const int mat = lane >> 3, r8 = lane & 7;
#pragma unroll
        for (int half = 0; half < 2; half++) {
            const int mt = warp + 8 * half;
            const int t = mt >> 1;
            mbar_wait(full(5 + t), 0);
            float acc0[4] = {0.f, 0.f, 0.f, 0.f}, acc1[4] = {0.f, 0.f, 0.f, 0.f};
            const int row = (mt & 1) * 16 + (mat & 1) * 8 + r8;
#pragma unroll
            for (int s = 0; s < 16; s++) {
                uint32_t a[4];
                ldsm_x4(a, swz<128>(slot(5 + t) + (s >> 2) * 4096, row, (s & 3) * 2 + (mat >> 1)));
                if (s & 1) mma_bf16(acc1, a, qb[2 * s], qb[2 * s + 1]);
                else mma_bf16(acc0, a, qb[2 * s], qb[2 * s + 1]);
            }
            __syncwarp();
            if (lane == 0) mbar_arrive(empty(5 + t));
            if (j == 0) {
#pragma unroll
                for (int c = 0; c < 4; c++) {
                    float sv = bf16r(bf16r(acc0[c] + acc1[c]) * 0.0625f);
                    sc[(c & 1) * 256 + mt * 16 + g + (c >> 1) * 8] = sv;
                }
            }
        }
    }
    cons_sync();

    {
        const float s0 = sc[tid], s1 = sc[256 + tid];
        float m0 = warp_max(s0), m1 = warp_max(s1);
        if (lane == 0) { wm[warp] = m0; wm[8 + warp] = m1; }
        cons_sync();
        m0 = wm[0]; m1 = wm[8];
#pragma unroll
        for (int w = 1; w < 8; w++) { m0 = fmaxf(m0, wm[w]); m1 = fmaxf(m1, wm[8 + w]); }
        float l0 = warp_sum(__expf(s0 - m0)), l1 = warp_sum(__expf(s1 - m1));
        cons_sync();
        if (lane == 0) { wm[warp] = l0; wm[8 + warp] = l1; }
        cons_sync();
        if (tid < 4) {
            float v;
            if (tid & 1) {
                const float* p = wm + (tid >> 1) * 8;
                v = ((p[0] + p[1]) + (p[2] + p[3])) + ((p[4] + p[5]) + (p[6] + p[7]));
            } else {
                v = (tid >> 1) ? m1 : m0;
            }
            ll_store(g_st + ((size_t)(bat * HKV + hkv) * 4 + chunk) * 4 + tid, __float_as_uint(v), tag);
        }
        if (tid < 16) {
            stt[tid] = __uint_as_float(ll_poll(g_st + (size_t)(bat * HKV + hkv) * 16 + tid, tag));
        }
        cons_sync();
        float M0 = fmaxf(fmaxf(stt[0], stt[4]), fmaxf(stt[8], stt[12]));
        float M1 = fmaxf(fmaxf(stt[2], stt[6]), fmaxf(stt[10], stt[14]));
        float L0 = 0.f, L1 = 0.f;
#pragma unroll
        for (int c = 0; c < 4; c++) {
            L0 += stt[4 * c + 1] * __expf(stt[4 * c] - M0);
            L1 += stt[4 * c + 3] * __expf(stt[4 * c + 2] - M1);
        }
        __nv_bfloat16* pb = reinterpret_cast<__nv_bfloat16*>(pb_w);
        pb[tid] = __float2bfloat16_rn(__fdividef(__expf(s0 - M0), L0));
        pb[256 + tid] = __float2bfloat16_rn(__fdividef(__expf(s1 - M1), L1));
    }
    cons_sync();

    {
        float acc[2][4];
#pragma unroll
        for (int i = 0; i < 2; i++)
#pragma unroll
            for (int c = 0; c < 4; c++) acc[i][c] = 0.f;
        const int mat = lane >> 3, r8 = lane & 7;
#pragma unroll
        for (int tv = 0; tv < 8; tv++) {
            mbar_wait(full(tv), (has_ffn || tv < 2 || tv > 4) ? 1u : 0u);
#pragma unroll
            for (int ks = 0; ks < 2; ks++) {
                const int pw = (tv * 32 + ks * 16) >> 1;
                const uint32_t b0 = g < 2 ? pb_w[g * 128 + pw + j] : 0u;
                const uint32_t b1 = g < 2 ? pb_w[g * 128 + pw + 4 + j] : 0u;
                const int row = ks * 16 + (mat >> 1) * 8 + r8;
#pragma unroll
                for (int i = 0; i < 2; i++) {
                    uint32_t a[4];
                    ldsm_x4_t(a, swz<128>(slot(tv) + (warp >> 1) * 4096, row,
                                          (warp & 1) * 4 + i * 2 + (mat & 1)));
                    mma_bf16(acc[i], a, b0, b1);
                }
            }
        }
        if (j == 0) {
#pragma unroll
            for (int i = 0; i < 2; i++)
#pragma unroll
                for (int c = 0; c < 4; c++) {
                    const int h = c & 1;
                    const int w32 = i * 16 + g + (c >> 1) * 8;
                    ll_store(g_o + ((size_t)(hkv * 16 + h * 8 + warp) * 16 + rk) * 32 + w32,
                             __float_as_uint(acc[i][c]), tag);
                }
        }
    }

    float ffn_part = 0.f;
    if (cta < NOWN) {
        const int e = tid & 15, sg = tid >> 4;
        const unsigned long long* src = g_ffn + (size_t)cta * NFFN * 16 + e;
#pragma unroll
        for (int it = 0; it < 7; it++)
            ffn_part += __uint_as_float(ll_poll(src + (size_t)(sg + 16 * it) * 16, tag));
    }

    if (tid < 128) {
        const int bb = tid >> 5, dd = tid & 31;
        const unsigned long long* src = g_o + ((size_t)cta * 16 + bb * 4) * 32 + dd;
        float o0 = __uint_as_float(ll_poll(src, tag));
        float o1 = __uint_as_float(ll_poll(src + 32, tag));
        float o2 = __uint_as_float(ll_poll(src + 64, tag));
        float o3 = __uint_as_float(ll_poll(src + 96, tag));
        reinterpret_cast<__nv_bfloat16*>(os_w)[bb * 40 + dd] = __float2bfloat16_rn((o0 + o1) + (o2 + o3));
    }
    cons_sync();

    if (warp < 7) {
        const int mat = lane >> 3, r8 = lane & 7;
        uint32_t bq[4];
#pragma unroll
        for (int s = 0; s < 2; s++) {
            bq[2 * s] = g < 4 ? os_w[g * 20 + 8 * s + j] : 0u;
            bq[2 * s + 1] = g < 4 ? os_w[g * 20 + 8 * s + 4 + j] : 0u;
        }
        const int ws = warp < 4 ? 8 : 9;
        const uint32_t wbase = slot(ws) + (warp & 3) * 4096;
        mbar_wait(full(ws), 1);
#pragma unroll
        for (int i = 0; i < 4; i++) {
            float d[4] = {0.f, 0.f, 0.f, 0.f};
#pragma unroll
            for (int s = 0; s < 2; s++) {
                uint32_t a[4];
                ldsm_x4_t(a, swz<128>(wbase, s * 16 + (mat >> 1) * 8 + r8, i * 2 + (mat & 1)));
                mma_bf16(d, a, bq[2 * s], bq[2 * s + 1]);
            }
            if (j < 2) {
                const int mt = warp * 4 + i;
#pragma unroll
                for (int c = 0; c < 4; c++) {
                    const int bb = 2 * j + (c & 1), e = g + (c >> 1) * 8;
                    ll_store(g_att + ((size_t)(bb * 28 + mt) * NCTA + cta) * 16 + e,
                             __float_as_uint(d[c]), tag);
                }
            }
        }
    }

    if (cta < NOWN) {
        const int e = tid & 15, sg = tid >> 4;
        const unsigned long long* src = g_att + (size_t)cta * NCTA * 16 + e;
        float a = 0.f;
#pragma unroll
        for (int it = 0; it < 8; it++)
            a += __uint_as_float(ll_poll(src + (size_t)(sg + 16 * it) * 16, tag));
        red[sg * 16 + e] = a;
        red[256 + sg * 16 + e] = ffn_part;
        cons_sync();
        if (tid < 16) {
            float sa = 0.f, sf = 0.f;
#pragma unroll
            for (int s = 0; s < 16; s++) { sa += red[s * 16 + tid]; sf += red[256 + s * 16 + tid]; }
            const int fo = cta * 16 + tid;
            float xv = __bfloat162float(x[fo]);
            float r = bf16r(xv + bf16r(sa));
            r = r + bf16r(sf);
            out[fo] = __float2bfloat16_rn(r);
        }
        if (cta == 0 && tid == 0) {
            asm volatile("st.relaxed.gpu.global.u32 [%0], %1;" ::"l"(&g_epoch), "r"(tag) : "memory");
        }
    }
}

typedef CUresult (*EncodeTiledFn)(CUtensorMap*, CUtensorMapDataType, cuuint32_t, void*,
                                  const cuuint64_t*, const cuuint64_t*, const cuuint32_t*,
                                  const cuuint32_t*, CUtensorMapInterleave, CUtensorMapSwizzle,
                                  CUtensorMapL2promotion, CUtensorMapFloatOOBfill);

EncodeTiledFn get_encode_fn() {
    static EncodeTiledFn fn = nullptr;
    if (!fn) {
        void* p = nullptr;
        cudaDriverEntryPointQueryResult st;
        cudaGetDriverEntryPoint("cuTensorMapEncodeTiled", &p, cudaEnableDefault, &st);
        fn = reinterpret_cast<EncodeTiledFn>(p);
    }
    return fn;
}

CUtensorMap make_map(const void* base, uint64_t cols, uint64_t rows, uint32_t box_cols,
                     uint32_t box_rows, CUtensorMapSwizzle sw, CUtensorMapL2promotion prom) {
    CUtensorMap m;
    cuuint64_t dims[2] = {cols, rows};
    cuuint64_t strides[1] = {cols * 2};
    cuuint32_t box[2] = {box_cols, box_rows};
    cuuint32_t estr[2] = {1, 1};
    get_encode_fn()(&m, CU_TENSOR_MAP_DATA_TYPE_BFLOAT16, 2, const_cast<void*>(base), dims, strides,
                    box, estr, CU_TENSOR_MAP_INTERLEAVE_NONE, sw, prom,
                    CU_TENSOR_MAP_FLOAT_OOB_FILL_NONE);
    return m;
}

}

extern "C" void kernel_launch(void* const* d_in, const int* in_sizes, int n_in, void* d_out,
                              int out_size) {
    (void)in_sizes; (void)n_in; (void)out_size;
    const __nv_bfloat16* x = (const __nv_bfloat16*)d_in[0];
    const void* kc = d_in[1];
    const void* vc = d_in[2];
    const void* wq = d_in[3];
    const void* wo = d_in[4];
    const void* wg = d_in[6];
    const void* wu = d_in[7];
    const void* wd = d_in[8];

    CUtensorMap tk = make_map(kc, 256, (uint64_t)NB * HKV * SK, 64, 32, CU_TENSOR_MAP_SWIZZLE_128B,
                              CU_TENSOR_MAP_L2_PROMOTION_L2_128B);
    CUtensorMap tv = make_map(vc, 256, (uint64_t)NB * HKV * SK, 64, 32, CU_TENSOR_MAP_SWIZZLE_128B,
                              CU_TENSOR_MAP_L2_PROMOTION_L2_128B);
    CUtensorMap tq = make_map(wq, 4096, 448, 32, 224, CU_TENSOR_MAP_SWIZZLE_64B,
                              CU_TENSOR_MAP_L2_PROMOTION_L2_128B);
    CUtensorMap tg = make_map(wg, 1792, 448, 16, 224, CU_TENSOR_MAP_SWIZZLE_32B,
                              CU_TENSOR_MAP_L2_PROMOTION_L2_128B);
    CUtensorMap tu = make_map(wu, 1792, 448, 16, 224, CU_TENSOR_MAP_SWIZZLE_32B,
                              CU_TENSOR_MAP_L2_PROMOTION_L2_128B);
    CUtensorMap td = make_map(wd, 448, 1792, 64, 16, CU_TENSOR_MAP_SWIZZLE_128B,
                              CU_TENSOR_MAP_L2_PROMOTION_L2_128B);
    CUtensorMap to = make_map(wo, 448, 4096, 64, 32, CU_TENSOR_MAP_SWIZZLE_128B,
                              CU_TENSOR_MAP_L2_PROMOTION_L2_128B);

    cudaFuncSetAttribute(fused_decode_kernel, cudaFuncAttributeMaxDynamicSharedMemorySize,
                         SMEM_BYTES);
    fused_decode_kernel<<<NCTA, NTHREADS, SMEM_BYTES>>>(tk, tv, tq, tg, tu, td, to, x,
                                                        (__nv_bfloat16*)d_out);
}
```

```cpp
#include <cuda_runtime.h>
#include <cuda_bf16.h>
#include <cuda.h>
#include <stdint.h>

namespace {

constexpr int NB   = 4;
constexpr int DM   = 448;
constexpr int HKV  = 8;
constexpr int SK   = 4096;
constexpr int WIN  = 1024;
constexpr int NCTA = 128;
constexpr int NFFN = 112;
constexpr int NOWN = 112;
constexpr int NTHREADS = 288;
constexpr int TMA_WINDOW = 3;

constexpr int SLOT  = 16384;
constexpr int NSLOT = 13;

constexpr int OFF_BAR = NSLOT * SLOT;
constexpr int OFF_XN  = OFF_BAR + 256;
constexpr int OFF_QS  = OFF_XN + 4 * 228 * 4;
constexpr int OFF_SC  = OFF_QS + 1024;
constexpr int OFF_PB  = OFF_SC + 2048;
constexpr int OFF_HS  = OFF_PB + 1024;
constexpr int OFF_OS  = OFF_HS + 256;
constexpr int OFF_WM  = OFF_OS + 512;
constexpr int OFF_ST  = OFF_WM + 128;
constexpr int OFF_RED = OFF_ST + 128;
constexpr int SMEM_USED = OFF_RED + 2048;
constexpr int SMEM_BYTES = SMEM_USED + 1024;

__device__ unsigned int g_epoch;
__device__ unsigned int g_err;
__device__ __align__(128) unsigned long long g_q[HKV * NB * 512];
__device__ __align__(128) unsigned long long g_st[NB * HKV * 4 * 4];
__device__ __align__(128) unsigned long long g_o[NCTA * 16 * 32];
__device__ __align__(128) unsigned long long g_att[NOWN * NCTA * 16];
__device__ __align__(128) unsigned long long g_ffn[NOWN * NFFN * 16];

constexpr unsigned SPIN_LIMIT = 1u << 22;


__device__ __forceinline__ uint32_t smem_u32(const void* p) {
    return (uint32_t)__cvta_generic_to_shared(p);
}
__device__ __forceinline__ void mbar_init(uint32_t a, uint32_t cnt) {
    asm volatile("mbarrier.init.shared::cta.b64 [%0], %1;" ::"r"(a), "r"(cnt) : "memory");
}
__device__ __forceinline__ void mbar_expect_tx(uint32_t a, uint32_t bytes) {
    asm volatile("mbarrier.arrive.expect_tx.shared::cta.b64 _, [%0], %1;" ::"r"(a), "r"(bytes)
                 : "memory");
}
__device__ __forceinline__ void mbar_arrive(uint32_t a) {
    asm volatile("mbarrier.arrive.shared::cta.b64 _, [%0];" ::"r"(a) : "memory");
}
__device__ __forceinline__ bool mbar_try(uint32_t a, uint32_t parity) {
    uint32_t ok;
    asm volatile(
        "{\n\t.reg .pred p;\n\t"
        "mbarrier.try_wait.parity.shared::cta.b64 p, [%1], %2;\n\t"
        "selp.u32 %0, 1, 0, p;\n\t}"
        : "=r"(ok)
        : "r"(a), "r"(parity)
        : "memory");
    return ok != 0;
}
__device__ __forceinline__ void mbar_wait(uint32_t a, uint32_t parity) {
    unsigned it = 0;
    while (!mbar_try(a, parity)) {
        if (++it > SPIN_LIMIT) { g_err = 1; break; }
    }
}
__device__ __forceinline__ void tma_2d(uint32_t dst, const CUtensorMap* tm, int c0, int c1,
                                       uint32_t mbar) {
    asm volatile(
        "cp.async.bulk.tensor.2d.shared::cluster.global.mbarrier::complete_tx::bytes "
        "[%0], [%1, {%3, %4}], [%2];" ::"r"(dst),
        "l"(reinterpret_cast<uint64_t>(tm)), "r"(mbar), "r"(c0), "r"(c1)
        : "memory");
}
__device__ __forceinline__ void cp_async16(uint32_t dst, const void* src) {
    asm volatile("cp.async.cg.shared.global [%0], [%1], 16;" ::"r"(dst), "l"(src) : "memory");
}
__device__ __forceinline__ void cp_async_arrive(uint32_t mbar) {
    asm volatile("cp.async.mbarrier.arrive.noinc.shared::cta.b64 [%0];" ::"r"(mbar) : "memory");
}
__device__ __forceinline__ void ldsm_x4(uint32_t (&r)[4], uint32_t a) {
    asm volatile("ldmatrix.sync.aligned.m8n8.x4.shared.b16 {%0,%1,%2,%3}, [%4];"
                 : "=r"(r[0]), "=r"(r[1]), "=r"(r[2]), "=r"(r[3])
                 : "r"(a)
                 : "memory");
}
__device__ __forceinline__ void ldsm_x4_t(uint32_t (&r)[4], uint32_t a) {
    asm volatile("ldmatrix.sync.aligned.m8n8.x4.trans.shared.b16 {%0,%1,%2,%3}, [%4];"
                 : "=r"(r[0]), "=r"(r[1]), "=r"(r[2]), "=r"(r[3])
                 : "r"(a)
                 : "memory");
}
__device__ __forceinline__ void mma_bf16(float (&d)[4], const uint32_t (&a)[4], uint32_t b0,
                                         uint32_t b1) {
    asm volatile(
        "mma.sync.aligned.m16n8k16.row.col.f32.bf16.bf16.f32 {%0,%1,%2,%3}, {%4,%5,%6,%7}, "
        "{%8,%9}, {%0,%1,%2,%3};"
        : "+f"(d[0]), "+f"(d[1]), "+f"(d[2]), "+f"(d[3])
        : "r"(a[0]), "r"(a[1]), "r"(a[2]), "r"(a[3]), "r"(b0), "r"(b1));
}
__device__ __forceinline__ void cons_sync() {
    asm volatile("bar.sync 1, 256;" ::: "memory");
}
template <int RBYTES>
__device__ __forceinline__ uint32_t swz(uint32_t base, int row, int chunk) {
    constexpr uint32_t MASK = RBYTES == 128 ? 7u : (RBYTES == 64 ? 3u : 1u);
    uint32_t off = (uint32_t)row * RBYTES + (uint32_t)chunk * 16u;
    return base + (off ^ (((off >> 7) & MASK) << 4));
}
__device__ __forceinline__ float bf16r(float v) {
    return __bfloat162float(__float2bfloat16_rn(v));
}
__device__ __forceinline__ uint32_t pack_bf16(float lo, float hi) {
    __nv_bfloat162 v = __floats2bfloat162_rn(lo, hi);
    return *reinterpret_cast<uint32_t*>(&v);
}
__device__ __forceinline__ void ll_store(unsigned long long* p, uint32_t payload, uint32_t tag) {
    unsigned long long v = ((unsigned long long)tag << 32) | payload;
    asm volatile("st.relaxed.gpu.global.b64 [%0], %1;" ::"l"(p), "l"(v) : "memory");
}
__device__ __forceinline__ uint32_t ll_poll(const unsigned long long* p, uint32_t tag) {
    unsigned long long v;
    unsigned it = 0;
    while (true) {
        asm volatile("ld.relaxed.gpu.global.b64 %0, [%1];" : "=l"(v) : "l"(p) : "memory");
        if ((uint32_t)(v >> 32) == tag) break;
        if (++it > SPIN_LIMIT) { g_err = 2; break; }
    }
    return (uint32_t)v;
}
template <int N>
__device__ __forceinline__ void ll_poll_n(const unsigned long long* p, size_t stride, uint32_t tag,
                                          float (&out)[N]) {
    unsigned it = 0;
    while (true) {
        unsigned long long v[N];
#pragma unroll
        for (int i = 0; i < N; i++)
            asm volatile("ld.relaxed.gpu.global.b64 %0, [%1];" : "=l"(v[i]) : "l"(p + i * stride) : "memory");
        bool ok = true;
#pragma unroll
        for (int i = 0; i < N; i++) {
            ok = ok && ((uint32_t)(v[i] >> 32) == tag);
            out[i] = __uint_as_float((uint32_t)v[i]);
        }
        if (ok) break;
        if (++it > SPIN_LIMIT) { g_err = 2; break; }
    }
}
__device__ __forceinline__ float warp_max(float v) {
#pragma unroll
    for (int o = 16; o > 0; o >>= 1) v = fmaxf(v, __shfl_xor_sync(0xffffffffu, v, o));
    return v;
}
__device__ __forceinline__ float warp_sum(float v) {
#pragma unroll
    for (int o = 16; o > 0; o >>= 1) v += __shfl_xor_sync(0xffffffffu, v, o);
    return v;
}
__device__ __forceinline__ float gelu_tanh(float x) {
    const float kBeta = 0.7978845608028654f, kKappa = 0.044715f;
    float inner = kBeta * (x + kKappa * x * x * x);
    return 0.5f * x * (1.0f + tanhf(inner));
}

__global__ void __launch_bounds__(NTHREADS, 1)
fused_decode_kernel(const __grid_constant__ CUtensorMap tm_k, const __grid_constant__ CUtensorMap tm_v,
                    const __grid_constant__ CUtensorMap tm_wq, const __grid_constant__ CUtensorMap tm_wd,
                    const __grid_constant__ CUtensorMap tm_wo, const __nv_bfloat16* __restrict__ wg,
                    const __nv_bfloat16* __restrict__ wu, const __nv_bfloat16* __restrict__ x,
                    __nv_bfloat16* __restrict__ out) {
    extern __shared__ uint8_t smem_raw[];
    uint8_t* smem = smem_raw + ((1024u - (smem_u32(smem_raw) & 1023u)) & 1023u);
    const uint32_t sb = smem_u32(smem);

    const int tid = threadIdx.x, warp = tid >> 5, lane = tid & 31;
    const int g = lane >> 2, j = lane & 3;
    const int cta = blockIdx.x;
    const int hkv = cta >> 4, rk = cta & 15;
    const int bat = rk >> 2, chunk = rk & 3;
    const bool has_ffn = cta < NFFN;

    auto full = [&](int s) { return sb + OFF_BAR + 8u * s; };
    auto empty = [&](int s) { return sb + OFF_BAR + 8u * (NSLOT + s); };
    auto slot = [&](int s) { return sb + (uint32_t)s * SLOT; };
    const uint32_t gu_full = sb + OFF_BAR + 8u * (2 * NSLOT);

    unsigned int epoch = 0;
    uint32_t xraw[7];
    unsigned short xown = 0;
    if (tid < 16 && cta < NOWN)
        asm volatile("ld.global.nc.u16 %0, [%1];" : "=h"(xown) : "l"(x + cta * 16 + tid) : "memory");
    if (warp < 8) {
        asm volatile("ld.relaxed.gpu.global.u32 %0, [%1];" : "=r"(epoch) : "l"(&g_epoch) : "memory");
        if (warp >= 4) {
            const uint32_t* xw = reinterpret_cast<const uint32_t*>(x) + (warp - 4) * (DM / 2) + lane;
#pragma unroll
            for (int e = 0; e < 7; e++)
                asm volatile("ld.global.nc.u32 %0, [%1];" : "=r"(xraw[e]) : "l"(xw + 32 * e) : "memory");
        }
    }
    if (tid == 0) {
        for (int s = 0; s < NSLOT; s++) mbar_init(full(s), 1);
        mbar_init(gu_full, 128);
        mbar_init(empty(0), 2);
        mbar_init(empty(1), 2);
        mbar_init(empty(2), 1);
        mbar_init(empty(3), 1);
        for (int s = 4; s < NSLOT; s++) mbar_init(empty(s), 2);
        asm volatile("fence.mbarrier_init.release.cluster;" ::: "memory");
        asm volatile("fence.proxy.async.shared::cta;" ::: "memory");
    }
    __syncthreads();

    if (warp == 8) {
        if (lane == 0) {
            asm volatile("prefetch.tensormap [%0];" ::"l"(reinterpret_cast<uint64_t>(&tm_wq)) : "memory");
            asm volatile("prefetch.tensormap [%0];" ::"l"(reinterpret_cast<uint64_t>(&tm_k)) : "memory");
            asm volatile("prefetch.tensormap [%0];" ::"l"(reinterpret_cast<uint64_t>(&tm_v)) : "memory");
            asm volatile("prefetch.tensormap [%0];" ::"l"(reinterpret_cast<uint64_t>(&tm_wd)) : "memory");
            asm volatile("prefetch.tensormap [%0];" ::"l"(reinterpret_cast<uint64_t>(&tm_wo)) : "memory");
            const int krow0 = (bat * HKV + hkv) * SK + (SK - WIN) + chunk * 256;
            auto landed = [&](int n) {
                if (n < 2) mbar_wait(full(n), 0);
                else if (n < 10) mbar_wait(full(4 + n - 2), 0);
                else if (n < 18) { const int v = n - 10; mbar_wait(full(v == 0 ? 12 : v - 1), (v == 1 || v == 2 || v > 4) ? 1u : 0u); }
                else if (n == 18) { if (has_ffn) mbar_wait(full(7), 1); }
                else mbar_wait(full(8 + n - 19), 1);
            };
#pragma unroll 1
            for (int n = 0; n < 21; n++) {
                const int wdw = TMA_WINDOW;
                if (n >= wdw) landed(n - wdw);
                if (n < 2) {
                    mbar_expect_tx(full(n), 14336);
                    tma_2d(slot(n), &tm_wq, 32 * cta, 224 * n, full(n));
                } else if (n < 10) {
                    const int t = n - 2;
                    mbar_expect_tx(full(4 + t), 16384);
                    for (int dg = 0; dg < 4; dg++)
                        tma_2d(slot(4 + t) + dg * 4096, &tm_k, 64 * dg, krow0 + 32 * t, full(4 + t));
                } else if (n < 18) {
                    const int v = n - 10, sl = v == 0 ? 12 : v - 1;
                    if (v > 0 && (has_ffn || v < 3 || v > 4)) mbar_wait(empty(sl), 0);
                    mbar_expect_tx(full(sl), 16384);
                    for (int dg = 0; dg < 4; dg++)
                        tma_2d(slot(sl) + dg * 4096, &tm_v, 64 * dg, krow0 + 32 * v, full(sl));
                } else if (n == 18) {
                    if (has_ffn) {
                        mbar_wait(empty(7), 0);
                        mbar_expect_tx(full(7), 14336);
                        for (int bx = 0; bx < 7; bx++)
                            tma_2d(slot(7) + bx * 2048, &tm_wd, 64 * bx, 16 * cta, full(7));
                    }
                } else if (n == 19) {
                    mbar_wait(empty(8), 0);
                    mbar_expect_tx(full(8), 16384);
                    for (int bx = 0; bx < 4; bx++)
                        tma_2d(slot(8) + bx * 4096, &tm_wo, 64 * bx, 32 * cta, full(8));
                } else {
                    mbar_wait(empty(9), 0);
                    mbar_expect_tx(full(9), 12288);
                    for (int bx = 4; bx < 7; bx++)
                        tma_2d(slot(9) + (bx - 4) * 4096, &tm_wo, 64 * bx, 32 * cta, full(9));
                }
            }
        }
        return;
    }

    uint32_t* xn_w = reinterpret_cast<uint32_t*>(smem + OFF_XN);
    uint32_t* qs_w = reinterpret_cast<uint32_t*>(smem + OFF_QS);
    float* sc = reinterpret_cast<float*>(smem + OFF_SC);
    uint32_t* pb_w = reinterpret_cast<uint32_t*>(smem + OFF_PB);
    uint32_t* hs_w = reinterpret_cast<uint32_t*>(smem + OFF_HS);
    uint32_t* os_w = reinterpret_cast<uint32_t*>(smem + OFF_OS);
    float* wm = reinterpret_cast<float*>(smem + OFF_WM);
    float* stt = reinterpret_cast<float*>(smem + OFF_ST);
    float* red = reinterpret_cast<float*>(smem + OFF_RED);

    if (warp < 4) {
        if (has_ffn) {
            const __nv_bfloat16* srcg = wg + 16 * cta;
            const __nv_bfloat16* srcu = wu + 16 * cta;
#pragma unroll
            for (int i = 0; i < 7; i++) {
                const int pc = tid + 128 * i;
                const int row = pc >> 1, ch = pc & 1;
                const uint32_t off = (uint32_t)(row % 224) * 32u + ch * 16u;
                const uint32_t sw = off ^ (((off >> 7) & 1u) << 4);
                const uint32_t half = (uint32_t)(row / 224) * 7168u;
                cp_async16(slot(2) + half + sw, srcg + (size_t)row * 1792 + ch * 8);
                cp_async16(slot(3) + half + sw, srcu + (size_t)row * 1792 + ch * 8);
            }
        }
        cp_async_arrive(gu_full);
    }
    const uint32_t tag = epoch + 1u;
    const uint32_t ntag = ~tag;

    if (warp < 2 && j < 2) {
        unsigned long long* dst = g_q + (size_t)(hkv * NB) * 512 + rk * 32 + warp * 16 + g;
#pragma unroll
        for (int c = 0; c < 4; c++) ll_store(dst + (2 * j + (c & 1)) * 512 + (c >> 1) * 8, 0u, ntag);
    }
    if (tid >= 64 && tid < 68)
        ll_store(g_st + ((size_t)(bat * HKV + hkv) * 4 + chunk) * 4 + (tid - 64), 0u, ntag);

    if (warp >= 4) {
        const int br = warp - 4;
        float2 v[7];
        float s = 0.f;
#pragma unroll
        for (int e = 0; e < 7; e++) {
            uint32_t u = xraw[e];
            __nv_bfloat162 h = *reinterpret_cast<__nv_bfloat162*>(&u);
            v[e] = __bfloat1622float2(h);
            s += v[e].x + v[e].y;
        }
        const float mean = warp_sum(s) * (1.0f / DM);
        float q2 = 0.f;
#pragma unroll
        for (int e = 0; e < 7; e++) {
            float a = v[e].x - mean, c = v[e].y - mean;
            q2 += a * a + c * c;
        }
        const float var = warp_sum(q2) * (1.0f / DM);
        const float m_b = bf16r(mean), v_b = bf16r(var);
        const float den = bf16r(sqrtf(bf16r(v_b + 1e-5f)));
#pragma unroll
        for (int e = 0; e < 7; e++) {
            float a = bf16r(v[e].x - m_b) / den, c = bf16r(v[e].y - m_b) / den;
            xn_w[br * 228 + lane + 32 * e] = pack_bf16(a, c);
        }
    }
    cons_sync();

    if (warp < 2) {
        float acc0[4] = {0.f, 0.f, 0.f, 0.f}, acc1[4] = {0.f, 0.f, 0.f, 0.f};
        const int mat = lane >> 3, r8 = lane & 7;
#pragma unroll
        for (int h = 0; h < 2; h++) {
            mbar_wait(full(h), 0);
#pragma unroll
            for (int ks = 0; ks < 14; ks++) {
                uint32_t a[4];
                ldsm_x4_t(a, swz<64>(slot(h), ks * 16 + (mat >> 1) * 8 + r8, warp * 2 + (mat & 1)));
                const int kw = (h * 14 + ks) * 8;
                uint32_t b0 = g < 4 ? xn_w[g * 228 + kw + j] : 0u;
                uint32_t b1 = g < 4 ? xn_w[g * 228 + kw + 4 + j] : 0u;
                if (ks & 1) mma_bf16(acc1, a, b0, b1);
                else mma_bf16(acc0, a, b0, b1);
            }
            __syncwarp();
            if (lane == 0) mbar_arrive(empty(h));
        }
        if (j < 2) {
            unsigned long long* dst = g_q + (size_t)(hkv * NB) * 512 + rk * 32 + warp * 16 + g;
#pragma unroll
            for (int c = 0; c < 4; c++) {
                const int bb = 2 * j + (c & 1), nn = (c >> 1) * 8;
                float qv = bf16r(acc0[c] + acc1[c]);
                ll_store(dst + bb * 512 + nn, __float_as_uint(qv), tag);
            }
        }
    } else if (warp == 2 && has_ffn) {
        float ag[4] = {0.f, 0.f, 0.f, 0.f}, au[4] = {0.f, 0.f, 0.f, 0.f};
        const int mat = lane >> 3, r8 = lane & 7;
        mbar_wait(gu_full, 0);
#pragma unroll
        for (int h = 0; h < 2; h++) {
#pragma unroll
            for (int ks = 0; ks < 14; ks++) {
                uint32_t a[4], a2[4];
                const int row = ks * 16 + (mat >> 1) * 8 + r8;
                ldsm_x4_t(a, swz<32>(slot(2) + h * 7168, row, mat & 1));
                ldsm_x4_t(a2, swz<32>(slot(3) + h * 7168, row, mat & 1));
                const int kw = (h * 14 + ks) * 8;
                uint32_t b0 = g < 4 ? xn_w[g * 228 + kw + j] : 0u;
                uint32_t b1 = g < 4 ? xn_w[g * 228 + kw + 4 + j] : 0u;
                mma_bf16(ag, a, b0, b1);
                mma_bf16(au, a2, b0, b1);
            }
        }
        __syncwarp();
        if (lane == 0) { mbar_arrive(empty(2)); mbar_arrive(empty(3)); }
        if (j < 2) {
            __nv_bfloat16* hs = reinterpret_cast<__nv_bfloat16*>(hs_w);
#pragma unroll
            for (int c = 0; c < 4; c++) {
                const int bb = 2 * j + (c & 1), ff = g + (c >> 1) * 8;
                float gv = bf16r(gelu_tanh(bf16r(ag[c])));
                float hv = gv * bf16r(au[c]);
                hs[bb * 24 + ff] = __float2bfloat16_rn(hv);
            }
        }
    }
    cons_sync();

    {
        const unsigned long long* src = g_q + (size_t)(hkv * NB + bat) * 512 + 2 * tid;
        float qv[2];
        ll_poll_n<2>(src, 1, tag, qv);
        qs_w[tid] = pack_bf16(qv[0], qv[1]);
    }
    cons_sync();

    if (j == 0) {
#pragma unroll
        for (int i = 0; i < 2; i++)
#pragma unroll
            for (int c = 0; c < 4; c++)
                ll_store(g_o + ((size_t)(hkv * 16 + (c & 1) * 8 + warp) * 16 + rk) * 32 + i * 16 + g + (c >> 1) * 8,
                         0u, ntag);
    }
    {
        uint32_t qb[32];
#pragma unroll
        for (int s = 0; s < 16; s++) {
            qb[2 * s] = g < 2 ? qs_w[g * 128 + 8 * s + j] : 0u;
            qb[2 * s + 1] = g < 2 ? qs_w[g * 128 + 8 * s + 4 + j] : 0u;
        }
        const int mat = lane >> 3, r8 = lane & 7;
#pragma unroll
        for (int half = 0; half < 2; half++) {
            const int mt = warp + 8 * half;
            const int t = mt >> 1;
            mbar_wait(full(4 + t), 0);
            float acc0[4] = {0.f, 0.f, 0.f, 0.f}, acc1[4] = {0.f, 0.f, 0.f, 0.f};
            const int row = (mt & 1) * 16 + (mat & 1) * 8 + r8;
#pragma unroll
            for (int s = 0; s < 16; s++) {
                uint32_t a[4];
                ldsm_x4(a, swz<128>(slot(4 + t) + (s >> 2) * 4096, row, (s & 3) * 2 + (mat >> 1)));
                if (s & 1) mma_bf16(acc1, a, qb[2 * s], qb[2 * s + 1]);
                else mma_bf16(acc0, a, qb[2 * s], qb[2 * s + 1]);
            }
            __syncwarp();
            if (lane == 0) mbar_arrive(empty(4 + t));
            if (j == 0) {
#pragma unroll
                for (int c = 0; c < 4; c++) {
                    float sv = bf16r(bf16r(acc0[c] + acc1[c]) * 0.0625f);
                    sc[(c & 1) * 256 + mt * 16 + g + (c >> 1) * 8] = sv;
                }
            }
        }
    }
    cons_sync();

    if (warp < 7 && j < 2) {
#pragma unroll
        for (int i = 0; i < 4; i++)
#pragma unroll
            for (int c = 0; c < 4; c++)
                ll_store(g_att + ((size_t)((2 * j + (c & 1)) * 28 + warp * 4 + i) * NCTA + cta) * 16 + g + (c >> 1) * 8,
                         0u, ntag);
    }
    if (has_ffn && warp < 7 && j < 2) {
#pragma unroll
        for (int i = 0; i < 4; i++)
#pragma unroll
            for (int c = 0; c < 4; c++)
                ll_store(g_ffn + ((size_t)((2 * j + (c & 1)) * 28 + warp * 4 + i) * NFFN + cta) * 16 + g + (c >> 1) * 8,
                         0u, ntag);
    }
    {
        const float s0 = sc[tid], s1 = sc[256 + tid];
        float m0 = warp_max(s0), m1 = warp_max(s1);
        if (lane == 0) { wm[warp] = m0; wm[8 + warp] = m1; }
        cons_sync();
        m0 = wm[0]; m1 = wm[8];
#pragma unroll
        for (int w = 1; w < 8; w++) { m0 = fmaxf(m0, wm[w]); m1 = fmaxf(m1, wm[8 + w]); }
        float l0 = warp_sum(__expf(s0 - m0)), l1 = warp_sum(__expf(s1 - m1));
        cons_sync();
        if (lane == 0) { wm[warp] = l0; wm[8 + warp] = l1; }
        cons_sync();
        if (tid < 4) {
            float v;
            if (tid & 1) {
                const float* p = wm + (tid >> 1) * 8;
                v = ((p[0] + p[1]) + (p[2] + p[3])) + ((p[4] + p[5]) + (p[6] + p[7]));
            } else {
                v = (tid >> 1) ? m1 : m0;
            }
            ll_store(g_st + ((size_t)(bat * HKV + hkv) * 4 + chunk) * 4 + tid, __float_as_uint(v), tag);
        }
        if (tid < 16) {
            stt[tid] = __uint_as_float(ll_poll(g_st + (size_t)(bat * HKV + hkv) * 16 + tid, tag));
        }
        cons_sync();
        float M0 = fmaxf(fmaxf(stt[0], stt[4]), fmaxf(stt[8], stt[12]));
        float M1 = fmaxf(fmaxf(stt[2], stt[6]), fmaxf(stt[10], stt[14]));
        float L0 = 0.f, L1 = 0.f;
#pragma unroll
        for (int c = 0; c < 4; c++) {
            L0 += stt[4 * c + 1] * __expf(stt[4 * c] - M0);
            L1 += stt[4 * c + 3] * __expf(stt[4 * c + 2] - M1);
        }
        __nv_bfloat16* pb = reinterpret_cast<__nv_bfloat16*>(pb_w);
        pb[tid] = __float2bfloat16_rn(__fdividef(__expf(s0 - M0), L0));
        pb[256 + tid] = __float2bfloat16_rn(__fdividef(__expf(s1 - M1), L1));
    }
    cons_sync();

    {
        float acc[2][4];
#pragma unroll
        for (int i = 0; i < 2; i++)
#pragma unroll
            for (int c = 0; c < 4; c++) acc[i][c] = 0.f;
        const int mat = lane >> 3, r8 = lane & 7;
#pragma unroll
        for (int tv = 0; tv < 8; tv++) {
            const int vs = tv == 0 ? 12 : tv - 1;
            mbar_wait(full(vs), (tv == 1 || tv == 2 || tv > 4) ? 1u : 0u);
#pragma unroll
            for (int ks = 0; ks < 2; ks++) {
                const int pw = (tv * 32 + ks * 16) >> 1;
                const uint32_t b0 = g < 2 ? pb_w[g * 128 + pw + j] : 0u;
                const uint32_t b1 = g < 2 ? pb_w[g * 128 + pw + 4 + j] : 0u;
                const int row = ks * 16 + (mat >> 1) * 8 + r8;
#pragma unroll
                for (int i = 0; i < 2; i++) {
                    uint32_t a[4];
                    ldsm_x4_t(a, swz<128>(slot(vs) + (warp >> 1) * 4096, row,
                                          (warp & 1) * 4 + i * 2 + (mat & 1)));
                    mma_bf16(acc[i], a, b0, b1);
                }
            }
        }
        if (j == 0) {
#pragma unroll
            for (int i = 0; i < 2; i++)
#pragma unroll
                for (int c = 0; c < 4; c++) {
                    const int h = c & 1;
                    const int w32 = i * 16 + g + (c >> 1) * 8;
                    ll_store(g_o + ((size_t)(hkv * 16 + h * 8 + warp) * 16 + rk) * 32 + w32,
                             __float_as_uint(acc[i][c]), tag);
                }
        }
    }

    if (has_ffn && warp < 7) {
        const int mat = lane >> 3, r8 = lane & 7;
        const uint32_t b0 = g < 4 ? hs_w[g * 12 + j] : 0u;
        const uint32_t b1 = g < 4 ? hs_w[g * 12 + 4 + j] : 0u;
        mbar_wait(full(7), 1);
#pragma unroll
        for (int i = 0; i < 4; i++) {
            uint32_t a[4];
            ldsm_x4_t(a, swz<128>(slot(7) + warp * 2048, (mat >> 1) * 8 + r8, i * 2 + (mat & 1)));
            float d[4] = {0.f, 0.f, 0.f, 0.f};
            mma_bf16(d, a, b0, b1);
            if (j < 2) {
                const int mt = warp * 4 + i;
#pragma unroll
                for (int c = 0; c < 4; c++) {
                    const int bb = 2 * j + (c & 1), e = g + (c >> 1) * 8;
                    ll_store(g_ffn + ((size_t)(bb * 28 + mt) * NFFN + cta) * 16 + e,
                             __float_as_uint(d[c]), tag);
                }
            }
        }
    }

    if (tid < 128) {
        const int bb = tid >> 5, dd = tid & 31;
        const unsigned long long* src = g_o + ((size_t)cta * 16 + bb * 4) * 32 + dd;
        float ov[4];
        ll_poll_n<4>(src, 32, tag, ov);
        reinterpret_cast<__nv_bfloat16*>(os_w)[bb * 40 + dd] =
            __float2bfloat16_rn((ov[0] + ov[1]) + (ov[2] + ov[3]));
    }
    cons_sync();

    if (warp < 7) {
        const int mat = lane >> 3, r8 = lane & 7;
        uint32_t bq[4];
#pragma unroll
        for (int s = 0; s < 2; s++) {
            bq[2 * s] = g < 4 ? os_w[g * 20 + 8 * s + j] : 0u;
            bq[2 * s + 1] = g < 4 ? os_w[g * 20 + 8 * s + 4 + j] : 0u;
        }
        const int ws = warp < 4 ? 8 : 9;
        const uint32_t wbase = slot(ws) + (warp & 3) * 4096;
        mbar_wait(full(ws), 1);
#pragma unroll
        for (int i = 0; i < 4; i++) {
            float d[4] = {0.f, 0.f, 0.f, 0.f};
#pragma unroll
            for (int s = 0; s < 2; s++) {
                uint32_t a[4];
                ldsm_x4_t(a, swz<128>(wbase, s * 16 + (mat >> 1) * 8 + r8, i * 2 + (mat & 1)));
                mma_bf16(d, a, bq[2 * s], bq[2 * s + 1]);
            }
            if (j < 2) {
                const int mt = warp * 4 + i;
#pragma unroll
                for (int c = 0; c < 4; c++) {
                    const int bb = 2 * j + (c & 1), e = g + (c >> 1) * 8;
                    ll_store(g_att + ((size_t)(bb * 28 + mt) * NCTA + cta) * 16 + e,
                             __float_as_uint(d[c]), tag);
                }
            }
        }
    }

    if (cta < NOWN) {
        const int e = tid & 15, sg = tid >> 4;
        const unsigned long long* sa_p = g_att + (size_t)cta * NCTA * 16 + e + (size_t)sg * 16;
        const unsigned long long* sf_p = g_ffn + (size_t)cta * NFFN * 16 + e + (size_t)sg * 16;
        float a = 0.f, f = 0.f;
        {
            unsigned it = 0;
            while (true) {
                unsigned long long v[15];
#pragma unroll
                for (int i = 0; i < 8; i++)
                    asm volatile("ld.relaxed.gpu.global.b64 %0, [%1];" : "=l"(v[i]) : "l"(sa_p + i * 256) : "memory");
#pragma unroll
                for (int i = 0; i < 7; i++)
                    asm volatile("ld.relaxed.gpu.global.b64 %0, [%1];" : "=l"(v[8 + i]) : "l"(sf_p + i * 256) : "memory");
                bool ok = true;
#pragma unroll
                for (int i = 0; i < 15; i++) ok = ok && ((uint32_t)(v[i] >> 32) == tag);
                if (ok) {
#pragma unroll
                    for (int i = 0; i < 8; i++) a += __uint_as_float((uint32_t)v[i]);
#pragma unroll
                    for (int i = 0; i < 7; i++) f += __uint_as_float((uint32_t)v[8 + i]);
                    break;
                }
                if (++it > SPIN_LIMIT) { g_err = 3; break; }
            }
        }
        red[sg * 16 + e] = a;
        red[256 + sg * 16 + e] = f;
        cons_sync();
        if (tid < 16) {
            float sa = 0.f, sf = 0.f;
#pragma unroll
            for (int s = 0; s < 16; s++) { sa += red[s * 16 + tid]; sf += red[256 + s * 16 + tid]; }
            const int fo = cta * 16 + tid;
            float xv = __bfloat162float(__ushort_as_bfloat16(xown));
            float r = bf16r(xv + bf16r(sa));
            r = r + bf16r(sf);
            out[fo] = __float2bfloat16_rn(r);
        }
        if (cta == 0 && tid == 0) {
            asm volatile("st.relaxed.gpu.global.u32 [%0], %1;" ::"l"(&g_epoch), "r"(tag) : "memory");
        }
    }
}

typedef CUresult (*EncodeTiledFn)(CUtensorMap*, CUtensorMapDataType, cuuint32_t, void*,
                                  const cuuint64_t*, const cuuint64_t*, const cuuint32_t*,
                                  const cuuint32_t*, CUtensorMapInterleave, CUtensorMapSwizzle,
                                  CUtensorMapL2promotion, CUtensorMapFloatOOBfill);

EncodeTiledFn get_encode_fn() {
    static EncodeTiledFn fn = nullptr;
    if (!fn) {
        void* p = nullptr;
        cudaDriverEntryPointQueryResult st;
        cudaGetDriverEntryPoint("cuTensorMapEncodeTiled", &p, cudaEnableDefault, &st);
        fn = reinterpret_cast<EncodeTiledFn>(p);
    }
    return fn;
}

CUtensorMap make_map(const void* base, uint64_t cols, uint64_t rows, uint32_t box_cols,
                     uint32_t box_rows, CUtensorMapSwizzle sw, CUtensorMapL2promotion prom) {
    CUtensorMap m;
    cuuint64_t dims[2] = {cols, rows};
    cuuint64_t strides[1] = {cols * 2};
    cuuint32_t box[2] = {box_cols, box_rows};
    cuuint32_t estr[2] = {1, 1};
    get_encode_fn()(&m, CU_TENSOR_MAP_DATA_TYPE_BFLOAT16, 2, const_cast<void*>(base), dims, strides,
                    box, estr, CU_TENSOR_MAP_INTERLEAVE_NONE, sw, prom,
                    CU_TENSOR_MAP_FLOAT_OOB_FILL_NONE);
    return m;
}

}

extern "C" void kernel_launch(void* const* d_in, const int* in_sizes, int n_in, void* d_out,
                              int out_size) {
    (void)in_sizes; (void)n_in; (void)out_size;
    const __nv_bfloat16* x = (const __nv_bfloat16*)d_in[0];
    const void* kc = d_in[1];
    const void* vc = d_in[2];
    const void* wq = d_in[3];
    const void* wo = d_in[4];
    const void* wg = d_in[6];
    const void* wu = d_in[7];
    const void* wd = d_in[8];

    CUtensorMap tk = make_map(kc, 256, (uint64_t)NB * HKV * SK, 64, 32, CU_TENSOR_MAP_SWIZZLE_128B,
                              CU_TENSOR_MAP_L2_PROMOTION_L2_128B);
    CUtensorMap tv = make_map(vc, 256, (uint64_t)NB * HKV * SK, 64, 32, CU_TENSOR_MAP_SWIZZLE_128B,
                              CU_TENSOR_MAP_L2_PROMOTION_L2_128B);
    CUtensorMap tq = make_map(wq, 4096, 448, 32, 224, CU_TENSOR_MAP_SWIZZLE_64B,
                              CU_TENSOR_MAP_L2_PROMOTION_L2_128B);
    CUtensorMap td = make_map(wd, 448, 1792, 64, 16, CU_TENSOR_MAP_SWIZZLE_128B,
                              CU_TENSOR_MAP_L2_PROMOTION_L2_128B);
    CUtensorMap to = make_map(wo, 448, 4096, 64, 32, CU_TENSOR_MAP_SWIZZLE_128B,
                              CU_TENSOR_MAP_L2_PROMOTION_L2_128B);

    cudaFuncSetAttribute(fused_decode_kernel, cudaFuncAttributeMaxDynamicSharedMemorySize,
                         SMEM_BYTES);
    fused_decode_kernel<<<NCTA, NTHREADS, SMEM_BYTES>>>(tk, tv, tq, td, to,
                                                        (const __nv_bfloat16*)wg,
                                                        (const __nv_bfloat16*)wu, x,
                                                        (__nv_bfloat16*)d_out);
}
```
